```python
import torch

def _softmax(x, axis=-1):
    return torch.softmax(x, dim=axis)
def _gelu(x):
    return torch.nn.functional.gelu(x, approximate="tanh")
def _silu(x):
    return torch.nn.functional.silu(x)
def _sigmoid(x):
    return torch.sigmoid(x)
def _layernorm(x, axis=-1, eps=1e-5):
    m = x.mean(dim=axis, keepdim=True)
    v = x.var(dim=axis, keepdim=True, unbiased=False)
    return (x - m) / torch.sqrt(v + eps)
def _scatter_add(tgt, idx, src, axis=0):
    return tgt.clone().index_add_(axis, idx, src)
def _segment_sum(src, seg, n):
    out = torch.zeros((n,) + src.shape[1:], dtype=src.dtype)
    return out.index_add_(0, seg, src)
def _pad(x, pw):
    flat = tuple(v for pair in reversed(pw) for v in pair)
    return torch.nn.functional.pad(x, flat)

kernel_name = 'sequential_preLN__sliding_block_cached__glu_gated_bilinear__decode'

def setup_inputs():

    _w = (lambda a: (lambda t: t.to(torch.bfloat16) if t.is_floating_point() else t)(torch.as_tensor(a)))
    def _A_setup():
        B, Sq, D = 1, 1, 448
        Hq, Hkv, Sk, Dh = 16, 8, 65536, 256
        assert Hq % Hkv == 0, (Hq, Hkv)
        return {
            "x": _w((lambda *s: torch.randn(*s, dtype=torch.bfloat16) * 0.05)(B, Sq, D)),
            "k_cache": _w((lambda *s: torch.randn(*s, dtype=torch.bfloat16) * 1.6)(B, Hkv, Sk, Dh)),
            "v_cache": _w((lambda *s: torch.randn(*s, dtype=torch.bfloat16) * 0.8)(B, Hkv, Sk, Dh)),
            "wq": _w((lambda *s: torch.randn(*s, dtype=torch.bfloat16) * 1.6)(D, Hq * Dh) * (D ** -0.5)),
            "wo": _w((lambda *s: torch.randn(*s, dtype=torch.bfloat16) * 0.8)(Hq * Dh, D) * ((Hq * Dh) ** -0.5)),
        }
    _A_in = _A_setup()

    def _B_setup():
        B, S, D, F = 1, 1, 448, 1792
        return {
            "x": _w((lambda *s: torch.randn(*s, dtype=torch.bfloat16) * 0.05)(B, S, D)),
            "w_gate": _w((lambda *s: torch.randn(*s, dtype=torch.bfloat16) * 0.4)(D, F) * (D ** -0.5)),
            "w_up": _w((lambda *s: torch.randn(*s, dtype=torch.bfloat16) * 0.4)(D, F) * (D ** -0.5)),
            "w_down": _w((lambda *s: torch.randn(*s, dtype=torch.bfloat16) * 0.4)(F, D) * (F ** -0.5)),
        }
    _B_in = _B_setup()

    return {
        "A_x": _A_in["x"],
        "A_k_cache": _A_in["k_cache"],
        "A_v_cache": _A_in["v_cache"],
        "A_wq": _A_in["wq"],
        "A_wo": _A_in["wo"],
        "B_x": _B_in["x"],
        "B_w_gate": _B_in["w_gate"],
        "B_w_up": _B_in["w_up"],
        "B_w_down": _B_in["w_down"],
    }

def reference(A_x, A_k_cache, A_v_cache, A_wq, A_wo, B_x, B_w_gate, B_w_up, B_w_down):
    def _A_ref(x, k_cache, v_cache, wq, wo):
        B, Sq, D = x.shape
        Hq, Dh = 16, 256
        Hkv, Sk = k_cache.shape[1], k_cache.shape[2]
        W = min(4096, max(256, Sk // 4))
        rep = Hq // Hkv
        q = (lambda x, *d: x.permute(*d))((x @ wq).reshape(B, Sq, Hq, Dh), 0, 2, 1, 3)
        k = (lambda x, n, axis: torch.repeat_interleave(x, n, dim=axis))(k_cache[:, :, Sk - W:, :], rep, axis=1)
        v = (lambda x, n, axis: torch.repeat_interleave(x, n, dim=axis))(v_cache[:, :, Sk - W:, :], rep, axis=1)
        scores = torch.einsum("bhqd,bhkd->bhqk", q, k) * (Dh ** -0.5)
        p = _softmax(scores, axis=-1)
        o = torch.einsum("bhqk,bhkd->bhqd", p, v)
        return (lambda x, *d: x.permute(*d))(o, 0, 2, 1, 3).reshape(B, Sq, Hq * Dh) @ wo

    def _B_ref(x, w_gate, w_up, w_down):
        g = torch.einsum("bsd,df->bsf", x, w_gate)
        u = torch.einsum("bsd,df->bsf", x, w_up)
        h = g * u
        return torch.einsum("bsf,fd->bsd", h, w_down)

    x = A_x
    h = x + _A_ref(_layernorm(x, axis=-1), A_k_cache, A_v_cache, A_wq, A_wo)
    h2 = h + _B_ref(_layernorm(h, axis=-1), B_w_gate, B_w_up, B_w_down)
    return h2
```

```cpp
#include <cuda_runtime.h>
#include <cuda_bf16.h>
#include <cuda.h>
#include <stdint.h>

namespace {

constexpr int kD = 448;
constexpr int kDh = 256;
constexpr int kSk = 65536;
constexpr int kWin = 4096;
constexpr int kFF = 1792;
constexpr int kNCta = 128;
constexpr int kNFfn = 112;
constexpr int kOwner = kNCta - 1;
constexpr int kSlot = 16384;
constexpr int kNSlot = 13;
constexpr int kNItem = 23;
constexpr int kThreads = 544;
constexpr int kSpinLimit = 1 << 16;

constexpr int kTau = 670;
constexpr int kWoGap = 400;
constexpr int kFfnLag = 200;
constexpr int kFfnGap = 300;
constexpr int kNPoll = 4;
constexpr int kPollGap = 100;

struct Scratch {
  float hacc[kD / 8][64];
  float facc[kD / 4][64];
  uint32_t o[kNCta][512];
  uint32_t q[8][512];
  uint32_t st[8][16][8];
  uint32_t ready[32];
  uint32_t epoch[32];
};
__device__ __align__(1024) Scratch g_s;

struct Maps {
  CUtensorMap k, v, g, u;
};
struct Ptrs {
  const __nv_bfloat16 *x, *wq, *wo, *dn;
  __nv_bfloat16* out;
};


struct SmallSmem {
  float sc[2][256];
  uint32_t p[2][128];
  uint32_t qs[256];
  uint32_t xn[224];
  float qred[4][32];
  alignas(16) float wmax[2][8];
  float wsum[8];
  float red[2][7][32];
  alignas(16) float hs[2][8];
  alignas(16) float hv[kD];
  float r2d;
  alignas(16) float hh[7][16];
  alignas(16) float os[32];
  float lmax[2];
  alignas(16) float dummy[4];
  float fac[2];
  unsigned long long full[kNItem];
  unsigned long long freeb[9];
  unsigned long long qready, fready;
};
constexpr int kSmemBytes = kNSlot * kSlot + (int)sizeof(SmallSmem) + 1024;

enum {
  kBarInit = 1,
  kBarAttn = 2,
  kBarO = 3,
  kBarInit2 = 5,
  kBarOwn = 6,
  kBarRes = 7,
  kBarCs = 8,
  kBarGu = 9,
  kBarMail = 12,
  kBarFfn = 13,
};

__device__ __forceinline__ uint32_t smem_u32(const void* p) { return (uint32_t)__cvta_generic_to_shared(p); }
__device__ __forceinline__ void mbar_init(uint32_t a, int c) {
  asm volatile("mbarrier.init.shared::cta.b64 [%0], %1;" ::"r"(a), "r"(c) : "memory");
}
__device__ __forceinline__ void mbar_expect(uint32_t a, uint32_t bytes) {
  asm volatile("mbarrier.arrive.expect_tx.shared::cta.b64 _, [%0], %1;" ::"r"(a), "r"(bytes) : "memory");
}
__device__ __forceinline__ void mbar_arrive(uint32_t a) {
  asm volatile("mbarrier.arrive.shared::cta.b64 _, [%0];" ::"r"(a) : "memory");
}
__device__ __forceinline__ void mbar_wait1(uint32_t a) {
  asm volatile(
      "{\n.reg .pred p;\n.reg .u32 n;\n"
      "mov.u32 n, 0;\n"
      "WAIT_LOOP:\n"
      "mbarrier.try_wait.parity.shared::cta.b64 p, [%0], 0;\n"
      "@p bra WAIT_DONE;\n"
      "add.u32 n, n, 1;\n"
      "setp.lt.u32 p, n, 0x4000;\n"
      "@p bra WAIT_LOOP;\n"
      "WAIT_DONE:\n}" ::"r"(a)
      : "memory");
}
__device__ __forceinline__ void mbar_wait(uint32_t a) {
  mbar_wait1(a);
  __syncwarp();
}
__device__ __forceinline__ bool mbar_test(uint32_t a) {
  uint32_t ok;
  asm volatile("{\n.reg .pred p;\nmbarrier.test_wait.parity.shared::cta.b64 p, [%1], 0;\nselp.u32 %0, 1, 0, p;\n}"
               : "=r"(ok)
               : "r"(a)
               : "memory");
  return ok;
}
__device__ __forceinline__ uint32_t now_ns() {
  uint32_t c;
  asm volatile("mov.u32 %0, %%globaltimer_lo;" : "=r"(c));
  return c;
}
__device__ __forceinline__ uint64_t stream_policy() {
  uint64_t p;
  asm volatile("createpolicy.fractional.L2::evict_first.b64 %0, 1.0;" : "=l"(p));
  return p;
}
__device__ __forceinline__ void tma3d(uint32_t dst, const CUtensorMap* m, int c0, int c1, int c2, uint32_t bar, uint64_t pol) {
  asm volatile(
      "cp.async.bulk.tensor.3d.shared::cluster.global.mbarrier::complete_tx::bytes.L2::cache_hint [%0], [%1, {%3, %4, %5}], [%2], %6;" ::"r"(dst),
      "l"(m), "r"(bar), "r"(c0), "r"(c1), "r"(c2), "l"(pol)
      : "memory");
}
__device__ __forceinline__ void bulk1d(uint32_t dst, const void* src, uint32_t bytes, uint32_t bar, uint64_t pol) {
  asm volatile("cp.async.bulk.shared::cluster.global.mbarrier::complete_tx::bytes.L2::cache_hint [%0], [%1], %2, [%3], %4;" ::"r"(dst),
               "l"(src), "r"(bytes), "r"(bar), "l"(pol)
               : "memory");
}
__device__ __forceinline__ void ldsm4(uint32_t (&r)[4], uint32_t a) {
  asm volatile("ldmatrix.sync.aligned.m8n8.x4.shared.b16 {%0,%1,%2,%3}, [%4];"
               : "=r"(r[0]), "=r"(r[1]), "=r"(r[2]), "=r"(r[3])
               : "r"(a)
               : "memory");
}
__device__ __forceinline__ void ldsm4t(uint32_t (&r)[4], uint32_t a) {
  asm volatile("ldmatrix.sync.aligned.m8n8.x4.trans.shared.b16 {%0,%1,%2,%3}, [%4];"
               : "=r"(r[0]), "=r"(r[1]), "=r"(r[2]), "=r"(r[3])
               : "r"(a)
               : "memory");
}
__device__ __forceinline__ void mma16816(float (&c)[4], const uint32_t (&a)[4], uint32_t b0, uint32_t b1) {
  asm volatile(
      "mma.sync.aligned.m16n8k16.row.col.f32.bf16.bf16.f32 {%0,%1,%2,%3}, {%4,%5,%6,%7}, {%8,%9}, {%0,%1,%2,%3};"
      : "+f"(c[0]), "+f"(c[1]), "+f"(c[2]), "+f"(c[3])
      : "r"(a[0]), "r"(a[1]), "r"(a[2]), "r"(a[3]), "r"(b0), "r"(b1));
}
__device__ __forceinline__ uint4 ld_poll4(const uint32_t* p) {
  uint4 v;
  asm volatile("ld.relaxed.gpu.global.v4.u32 {%0,%1,%2,%3}, [%4];"
               : "=r"(v.x), "=r"(v.y), "=r"(v.z), "=r"(v.w)
               : "l"(p)
               : "memory");
  return v;
}
__device__ __forceinline__ void st_ll4(uint32_t* p, uint32_t a, uint32_t b, uint32_t c, uint32_t d) {
  asm volatile("st.relaxed.gpu.global.v4.u32 [%0], {%1,%2,%3,%4};" ::"l"(p), "r"(a), "r"(b), "r"(c), "r"(d) : "memory");
}
__device__ __forceinline__ uint32_t stale4(const uint4& v, uint32_t tag) {
  return ((v.x ^ tag) | (v.y ^ tag) | (v.z ^ tag) | (v.w ^ tag)) & 15u;
}
__device__ __forceinline__ uint32_t tagf(float f, uint32_t tag) {
  uint32_t r;
  asm("lop3.b32 %0, %1, 0xFFFFFFF0, %2, 0xEA;" : "=r"(r) : "r"(__float_as_uint(f)), "r"(tag));
  return r;
}
__device__ __forceinline__ void pin(uint32_t& v) { asm volatile("" : "+r"(v)); }
__device__ __forceinline__ void pin(float& v) { asm volatile("" : "+f"(v)); }
template <class T>
__device__ __forceinline__ void pin(T*& v) { asm volatile("" : "+l"(v)); }
__device__ __forceinline__ float4 lds128(uint32_t a) {
  float4 v;
  asm volatile("ld.shared.v4.f32 {%0,%1,%2,%3}, [%4];" : "=f"(v.x), "=f"(v.y), "=f"(v.z), "=f"(v.w) : "r"(a) : "memory");
  return v;
}
__device__ __forceinline__ uint32_t lds32(uint32_t a) {
  uint32_t v;
  asm volatile("ld.shared.u32 %0, [%1];" : "=r"(v) : "r"(a) : "memory");
  return v;
}
__device__ __forceinline__ void sts32(uint32_t a, float x) { asm volatile("st.shared.f32 [%0], %1;" ::"r"(a), "f"(x) : "memory"); }
__device__ __forceinline__ void red_pair(float* p, float a, float b) {
  asm volatile("red.relaxed.gpu.global.v4.f32.add [%0], {%1,%2,%3,%4};" ::"l"(p), "f"(a), "f"(b), "f"(1.f), "f"(0.f) : "memory");
}
__device__ __forceinline__ float4 ld_acc(const float* p) {
  float4 v;
  asm volatile("ld.relaxed.gpu.global.v4.f32 {%0,%1,%2,%3}, [%4];" : "=f"(v.x), "=f"(v.y), "=f"(v.z), "=f"(v.w) : "l"(p) : "memory");
  return v;
}
__device__ __forceinline__ void poll_acc(float4& v, const float* p, float n) {
  asm volatile(
      "{\n.reg .pred q;\n.reg .u32 it;\n"
      "mov.u32 it, 0;\n"
      "bra POLL_TEST;\n"
      "POLL_AGAIN:\n"
      "ld.relaxed.gpu.global.v4.f32 {%0,%1,%2,%3}, [%4];\n"
      "POLL_TEST:\n"
      "setp.eq.f32 q, %2, %5;\n"
      "vote.sync.all.pred q, q, 0xffffffff;\n"
      "@q bra POLL_DONE;\n"
      "add.u32 it, it, 1;\n"
      "setp.lt.u32 q, it, 0x10000;\n"
      "@q bra POLL_AGAIN;\n"
      "POLL_DONE:\n}"
      : "+f"(v.x), "+f"(v.y), "+f"(v.z), "+f"(v.w)
      : "l"(p), "f"(n)
      : "memory");
}
__device__ __forceinline__ void st_ll1(uint32_t* p, uint32_t a) {
  asm volatile("st.relaxed.gpu.global.u32 [%0], %1;" ::"l"(p), "r"(a) : "memory");
}
__device__ __forceinline__ void sts32_if(bool p, uint32_t a, float x) {
  asm volatile("{\n.reg .pred p;\nsetp.ne.u32 p, %2, 0;\n@p st.shared.f32 [%0], %1;\n}" ::"r"(a), "f"(x), "r"((uint32_t)p) : "memory");
}
__device__ __forceinline__ void st_ll4_if(bool p, uint32_t* ptr, uint32_t a, uint32_t b, uint32_t c, uint32_t d) {
  asm volatile("{\n.reg .pred p;\nsetp.ne.u32 p, %5, 0;\n@p st.relaxed.gpu.global.v4.u32 [%0], {%1,%2,%3,%4};\n}" ::"l"(ptr),
               "r"(a), "r"(b), "r"(c), "r"(d), "r"((uint32_t)p)
               : "memory");
}
__device__ __forceinline__ void ld_poll4_if(bool p, uint4& v, const uint32_t* ptr) {
  asm volatile("{\n.reg .pred p;\nsetp.ne.u32 p, %5, 0;\n@p ld.relaxed.gpu.global.v4.u32 {%0,%1,%2,%3}, [%4];\n}"
               : "+r"(v.x), "+r"(v.y), "+r"(v.z), "+r"(v.w)
               : "l"(ptr), "r"((uint32_t)p)
               : "memory");
}
template <int N>
__device__ __forceinline__ void keep_unpacked(const float (&wf)[N][2], uint32_t dummy, uint32_t key) {
  float u[4] = {0.f, 0.f, 0.f, 0.f};
#pragma unroll
  for (int r = 0; r < N; r++) u[r & 3] = fmaf(wf[r][0], wf[r][1], u[r & 3]);
  sts32_if(__float_as_uint((u[0] + u[1]) + (u[2] + u[3])) == key + 1, dummy, 0.f);
}
__device__ __forceinline__ float sum4(const float4& v) { return (v.x + v.y) + (v.z + v.w); }
__device__ __forceinline__ float untag(uint32_t u) { return __uint_as_float(u & ~15u); }
__device__ __forceinline__ float bfr(float f) {
  uint32_t r;
  asm("cvt.rn.bf16x2.f32 %0, %1, %2;" : "=r"(r) : "f"(f), "f"(0.f));
  return __uint_as_float(r);
}
__device__ __forceinline__ float sqrt_fast(float f) {
  float r;
  asm("sqrt.approx.ftz.f32 %0, %1;" : "=f"(r) : "f"(f));
  return r;
}
__device__ __forceinline__ float rcp_fast(float f) {
  float r;
  asm("rcp.approx.ftz.f32 %0, %1;" : "=f"(r) : "f"(f));
  return r;
}
__device__ __forceinline__ uint32_t pack2(float lo, float hi) {
  __nv_bfloat162 v = __floats2bfloat162_rn(lo, hi);
  return *reinterpret_cast<uint32_t*>(&v);
}
__device__ __forceinline__ float lo_f(uint32_t w) { return __uint_as_float(w << 16); }
__device__ __forceinline__ float hi_f(uint32_t w) { return __uint_as_float(w & 0xFFFF0000u); }
__device__ __forceinline__ void bar_sync(int id, int n) { asm volatile("bar.sync %0, %1;" ::"r"(id), "r"(n) : "memory"); }
__device__ __forceinline__ void bar_arrive(int id, int n) { asm volatile("bar.arrive %0, %1;" ::"r"(id), "r"(n) : "memory"); }

template <int N>
__device__ __forceinline__ bool poll_missing(uint4 (&v)[N], const uint32_t* p, uint32_t tag) {
#pragma unroll
  for (int i = 0; i < N; i++) ld_poll4_if(stale4(v[i], tag) != 0, v[i], p + 128 * i);
  uint32_t any = 0;
#pragma unroll
  for (int i = 0; i < N; i++) any |= stale4(v[i], tag);
  return __all_sync(0xffffffffu, any == 0);
}
__device__ __forceinline__ float4 as_f4(const uint4& v) {
  return make_float4(__uint_as_float(v.x), __uint_as_float(v.y), __uint_as_float(v.z), __uint_as_float(v.w));
}
__device__ __forceinline__ float4 add4(const float4& a, const float4& b) {
  return make_float4(a.x + b.x, a.y + b.y, a.z + b.z, a.w + b.w);
}
template <int HI = 16>
__device__ __forceinline__ float treduce2(const float4& s, int lane) {
  const bool up = lane & HI;
  float k0 = up ? s.z : s.x, k1 = up ? s.w : s.y;
  float g0 = up ? s.x : s.z, g1 = up ? s.y : s.w;
  k0 += __shfl_xor_sync(0xffffffffu, g0, HI);
  k1 += __shfl_xor_sync(0xffffffffu, g1, HI);
  const bool up2 = lane & (HI / 2);
  float k = up2 ? k1 : k0, g = up2 ? k0 : k1;
  return k + __shfl_xor_sync(0xffffffffu, g, HI / 2);
}

__global__ void __launch_bounds__(kThreads, 1)
fused_decode_kernel(const __grid_constant__ Maps maps, const Ptrs ptrs) {
  extern __shared__ uint8_t smem_raw[];
  const uint32_t ring = (smem_u32(smem_raw) + 1023u) & ~1023u;
  SmallSmem& sm = *reinterpret_cast<SmallSmem*>(smem_raw + (ring - smem_u32(smem_raw)) + kNSlot * kSlot);
  const int tid = threadIdx.x, w = tid >> 5, l = tid & 31;
  const int b = blockIdx.x;
  const int h = b >> 4, j = b & 15;
  const bool ffn = b < kNFfn;
  const uint32_t full0 = smem_u32(&sm.full[0]);
  const uint32_t free0 = smem_u32(&sm.freeb[0]);

  if (w == 8) {
    const int row0 = h * kSk + (kSk - kWin) + j * 32;
    const uint64_t pol = stream_policy();
    if (l == 0) {
      mbar_init(full0 + 8, 1);
      asm volatile("fence.proxy.async.shared::cta;" ::: "memory");
      mbar_expect(full0 + 8, kSlot);
      tma3d(ring, &maps.k, 0, row0, 0, full0 + 8, pol);
      mbar_init(full0, 256);
#pragma unroll
      for (int i = 2; i < kNItem + 11; i++) mbar_init(full0 + 8 * i, i == kNItem + 8 ? 8 : 1);
      asm volatile("fence.proxy.async.shared::cta;" ::: "memory");
      asm volatile("prefetch.tensormap [%0];" ::"l"(&maps.v) : "memory");
      asm volatile("prefetch.tensormap [%0];" ::"l"(&maps.g) : "memory");
      asm volatile("prefetch.tensormap [%0];" ::"l"(&maps.u) : "memory");
    }
    const uint32_t t0 = __shfl_sync(0xffffffffu, now_ns(), 0) - 100;
    bar_arrive(kBarInit, 288);
    bar_arrive(kBarInit2, 64);
    if (l == 0) {
      int spin = 0, due = 490;
#pragma unroll 1
      for (int i = 2; i <= 17; i++) {
        due += i == 17 ? 1220 : kTau;
        const uint32_t bar = full0 + 8 * i;
        while ((int)(now_ns() - t0) < due && !mbar_test(bar - 16) && ++spin < kSpinLimit) {}
        if (i == 17) {
          mbar_wait1(free0 + 8 * 3);
          mbar_wait1(free0 + 8 * 4);
          mbar_expect(bar, 28672);
          bulk1d(ring + 3 * kSlot, ptrs.wo + (size_t)b * 32 * kD, 14336, bar, pol);
          due = (int)(now_ns() - t0) + kWoGap;
          while ((int)(now_ns() - t0) < due && ++spin < kSpinLimit) {}
          bulk1d(ring + 3 * kSlot + 14336, ptrs.wo + (size_t)(b * 32 + 16) * kD, 14336, bar, pol);
        } else {
          if (i == 12) mbar_wait1(free0 + 8 * 8);
          if (i >= 14) mbar_wait1(free0 + 8 * (i - 14));
          mbar_expect(bar, kSlot);
          tma3d(ring + (i < 14 ? i - 1 : i - 14) * kSlot, i <= 8 ? &maps.k : &maps.v, 0, row0 + ((i - 1) & 7) * 512, 0, bar, pol);
        }
      }
      if (ffn) {
        mbar_wait1(free0 + 8 * 5);
        mbar_wait1(free0 + 8 * 6);
        mbar_wait1(free0 + 8 * 7);
        mbar_expect(full0 + 8 * 18, 14336);
#pragma unroll
        for (int c = 0; c < 4; c++) mbar_expect(full0 + 8 * (19 + c), 7168);
        mbar_wait1(smem_u32(&sm.fready));
        mbar_wait1(full0 + 8 * 16);
        due = (int)(now_ns() - t0) + kFfnLag;
#pragma unroll 1
        for (int c = 0; c < 4; c++) {
          while ((int)(now_ns() - t0) < due && ++spin < kSpinLimit) {}
          due += kFfnGap;
          tma3d(ring + 6 * kSlot + c * 3584, &maps.g, 16 * b, 0, 4 * c, full0 + 8 * (19 + c), pol);
          tma3d(ring + 6 * kSlot + 14336 + c * 3584, &maps.u, 16 * b, 0, 4 * c, full0 + 8 * (19 + c), pol);
        }
        while ((int)(now_ns() - t0) < due && ++spin < kSpinLimit) {}
        bulk1d(ring + 5 * kSlot, ptrs.dn + (size_t)b * 16 * kD, 14336, full0 + 8 * 18, pol);
      }
    }
    __syncwarp();
    if (ffn) bar_arrive(kBarFfn, 256);
    return;
  }
  auto poll_o = [&](int turn, uint32_t tag1) {
    uint32_t dst = smem_u32(&sm.os[l]), flag = smem_u32(&sm.os[0]);
    const uint32_t* src = &g_s.o[b][4 * l];
    pin(dst);
    pin(src);
    pin(tag1);
    uint4 v[4];
#pragma unroll
    for (int i = 0; i < 4; i++) v[i] = make_uint4(~tag1, 0, 0, 0);
    bar_sync(kBarO, 32 * kNPoll);
    if (turn) __nanosleep(turn * kPollGap);
    int it = 0;
    uint32_t pending;
#pragma unroll 1
    do {
      if (poll_missing<4>(v, src, tag1)) {
        const float o = bfr(treduce2(add4(add4(as_f4(v[0]), as_f4(v[1])), add4(as_f4(v[2]), as_f4(v[3]))), l));
        asm volatile("st.volatile.shared.f32 [%0], %1;" ::"r"(dst), "f"(o) : "memory");
        break;
      }
      asm volatile("ld.volatile.shared.u32 %0, [%1];" : "=r"(pending) : "r"(flag) : "memory");
    } while ((pending & 1) && ++it < kSpinLimit);
  };
  uint32_t epoch;
  asm volatile("ld.relaxed.gpu.global.u32 %0, [%1];" : "=r"(epoch) : "l"(&g_s.epoch[0]) : "memory");
  if (w >= 10 && !ffn && b != kOwner) {
    if (w < 8 + kNPoll) poll_o(w - 8, ((epoch + 1) << 2) | 1);
    return;
  }
  const int g = l >> 2, t = l & 3;
  uint32_t* odst = &g_s.o[16 * h + 8 * (t & 1) + (w & 7)][32 * j + 4 * g];
  const int wc = w >= 10 ? w - 10 : w < 7 ? w : 0;
  float* accp = &g_s.hacc[8 * wc + (l >> 2)][4 * (l & 3)];
  float* accf = &g_s.facc[16 * wc + (l >> 1)][4 * (l & 1)];
  if (w < 8) {
    st_ll4_if(t < 2, odst, 0, 0, 0, 0);
    if (w == 0) st_ll4_if(l < 10, l < 8 ? &g_s.q[h][32 * j + 4 * l] : &g_s.st[h][j][4 * (l - 8)], 0, 0, 0, 0);
  }
  if (w >= 10) {
    const uint32_t xw = *reinterpret_cast<const uint32_t*>(ptrs.x + 64 * (w - 10) + 2 * l);
    if (!ffn) {
      uint32_t *ah = reinterpret_cast<uint32_t*>(accp), *af = reinterpret_cast<uint32_t*>(accf);
      st_ll4(ah, xw << 16, xw & 0xFFFF0000u, 0, 0);
      st_ll4(af, 0, 0, 0, 0);
      uint32_t tag;
      asm volatile("{\n.reg .pred p, q;\nsetp.ne.u32 p, %1, 0;\nbar.red.or.pred q, %2, 224, p;\nselp.u32 %0, 1, 0, q;\n}"
                   : "=r"(tag)
                   : "r"(ld_poll4(ah).z | ld_poll4(af).z), "n"((int)kBarOwn)
                   : "memory");
      tag += (epoch + 1) << 2;
      if (w == 10) st_ll4_if(l < 2, &g_s.ready[4 * l], tag, tag, tag, tag);
      if (w < 8 + kNPoll) poll_o(w - 8, ((epoch + 1) << 2) | 1);
      return;
    }
    const int wb = w - 10, rg = (l >> 2) & 3;
    const uint32_t src = ring + 6 * kSlot + (l >> 4) * 14336 + (4 * wb + rg) * 32 + (l & 3) * 8;
    if (w < 8 + kNPoll) poll_o(w - 8, ((epoch + 1) << 2) | 1);
    bar_sync(kBarFfn, 256);
    float wf[16][4];
    float4 cs = make_float4(0.f, 0.f, 0.f, 0.f), hv;
#pragma unroll
    for (int i = 0; i < 16; i++) {
      if ((i & 3) == 0) mbar_wait(full0 + 8 * (19 + i / 4));
      if (i == 12) hv = ld_acc(accp);
      uint2 raw;
      asm volatile("ld.shared.v2.u32 {%0,%1}, [%2];" : "=r"(raw.x), "=r"(raw.y) : "r"(src + i * 896) : "memory");
      wf[i][0] = lo_f(raw.x); wf[i][1] = hi_f(raw.x); wf[i][2] = lo_f(raw.y); wf[i][3] = hi_f(raw.y);
      cs.x += wf[i][0]; cs.y += wf[i][1]; cs.z += wf[i][2]; cs.w += wf[i][3];
#pragma unroll
      for (int e = 0; e < 4; e++) pin(wf[i][e]);
      if ((i & 3) == 3 && i < 15) sts32_if(__float_as_uint(sum4(cs)) == epoch + 1, smem_u32(&sm.dummy), 0.f);
    }
    uint32_t rdst = smem_u32(&sm.red[0][wb][(l & 16) + 4 * (l & 3) + rg]);
    uint32_t hsa = smem_u32(&sm.hs[0][wb]);
    int sl = 8 * rg;
    pin(rdst);
    pin(accp);
    pin(hsa);
    asm volatile("" : "+r"(sl));
    sts32(rdst, treduce2<8>(cs, l));
    bar_arrive(kBarCs, 448);
    poll_acc(hv, accp, (float)kNCta);
    float4 acc = make_float4(0.f, 0.f, 0.f, 0.f), acc2 = acc;
    float s = (hv.x + hv.w) + hv.y;
#pragma unroll
    for (int i = 0; i < 8; i++) {
      const float f0 = __shfl_sync(0xffffffffu, hv.x, sl + i), f1 = __shfl_sync(0xffffffffu, hv.y, sl + i);
      if (i < 5) s += __shfl_xor_sync(0xffffffffu, s, 1 << i);
      acc.x = fmaf(f0, wf[2 * i][0], acc.x); acc.y = fmaf(f0, wf[2 * i][1], acc.y);
      acc.z = fmaf(f0, wf[2 * i][2], acc.z); acc.w = fmaf(f0, wf[2 * i][3], acc.w);
      acc2.x = fmaf(f1, wf[2 * i + 1][0], acc2.x); acc2.y = fmaf(f1, wf[2 * i + 1][1], acc2.y);
      acc2.z = fmaf(f1, wf[2 * i + 1][2], acc2.z); acc2.w = fmaf(f1, wf[2 * i + 1][3], acc2.w);
    }
    sts32_if(l == 0, hsa, s);
    sts32(rdst + 7 * 128, treduce2<8>(add4(acc, acc2), l));
    bar_arrive(kBarGu, 480);
    {
      uint32_t hd = smem_u32(&sm.hv[64 * wb + 2 * l]);
      asm volatile("st.shared.v2.f32 [%0], {%1,%2};" ::"r"(hd), "f"(hv.x), "f"(hv.y) : "memory");
      asm volatile("ld.volatile.shared.v2.f32 {%0,%1}, [%2];" : "=f"(hv.x), "=f"(hv.y) : "r"(hd) : "memory");
      float q = hv.x * hv.x + hv.y * hv.y;
#pragma unroll
      for (int o = 16; o; o >>= 1) q += __shfl_xor_sync(0xffffffffu, q, o);
      sts32_if(l == 0, hsa + 32, q);
      asm volatile("st.shared.v2.f32 [%0], {%1,%2};" ::"r"(hd), "f"(bfr(lo_f(xw) + bfr(hv.x - lo_f(xw)))),
                   "f"(bfr(hi_f(xw) + bfr(hv.y - hi_f(xw))))
                   : "memory");
      bar_arrive(kBarOwn, 256);
    }
    return;
  }

  if (w == 9) {
    const uint32_t tag = (epoch + 1) << 2;
    {
      uint4 v[4];
#pragma unroll
      for (int i = 0; i < 4; i++) v[i] = make_uint4(~tag, 0, 0, 0);
      int it = 0;
      bar_sync(kBarMail, 64);
#pragma unroll 1
      while (!poll_missing<4>(v, &g_s.q[h][4 * l], tag) && ++it < kSpinLimit) __nanosleep(200);
#pragma unroll
      for (int i = 0; i < 4; i++)
        *reinterpret_cast<uint2*>(&sm.qs[64 * i + 2 * l]) =
            make_uint2(__byte_perm(v[i].x, v[i].y, 0x7632), __byte_perm(v[i].z, v[i].w, 0x7632));
      bar_sync(kBarInit2, 64);
      if (l == 0) mbar_arrive(smem_u32(&sm.qready));
      it = 0;
#pragma unroll 1
      while (stale4(ld_poll4(&g_s.ready[0]), tag) && ++it < kSpinLimit) __nanosleep(300);
    }
    {
      uint4 v[1];
      v[0] = make_uint4(~tag, 0, 0, 0);
      int it = 0;
      bar_sync(kBarMail, 64);
#pragma unroll 1
      while (!poll_missing<1>(v, &g_s.st[h][l & 15][0], tag) && ++it < kSpinLimit) __nanosleep(300);
      const float mi_ = untag(l & 16 ? v[0].z : v[0].x), li_ = untag(l & 16 ? v[0].w : v[0].y);
      float M = mi_;
#pragma unroll
      for (int o = 8; o; o >>= 1) M = fmaxf(M, __shfl_xor_sync(0xffffffffu, M, o));
      const float e = __expf(mi_ - M);
      float L = li_ * e;
#pragma unroll
      for (int o = 8; o; o >>= 1) L += __shfl_xor_sync(0xffffffffu, L, o);
      if ((l & 15) == j) sm.fac[l >> 4] = __fdividef(e, L);
      __syncwarp();
      if (l == 0) mbar_arrive(smem_u32(&sm.fready));
    }
    poll_o(0, ((epoch + 1) << 2) | 1);
    if (ffn) {
      bar_sync(kBarGu, 480);
      bar_sync(kBarOwn, 256);
      const float mean = sum4(add4(lds128(smem_u32(&sm.hs[0][0])), lds128(smem_u32(&sm.hs[0][4])))) * (1.f / kD);
      const float q = sum4(add4(lds128(smem_u32(&sm.hs[1][0])), lds128(smem_u32(&sm.hs[1][4]))));
      const float rden = rcp_fast(bfr(sqrt_fast(bfr(bfr(fmaxf(q * (1.f / kD) - mean * mean, 0.f)) + 1e-5f))));
      if (l == 0) sm.r2d = rden * rden;
      bar_arrive(kBarRes, 256);
    }
    return;
  }

  const int mi = l >> 3, mr = l & 7;
  uint32_t xw[7];
  if (w == 0) {
#pragma unroll
    for (int i = 0; i < 7; i++)
      asm volatile("ld.global.nc.u32 %0, [%1];" : "=r"(xw[i]) : "l"(reinterpret_cast<const uint32_t*>(ptrs.x) + l + 32 * i));
  }
  {
    const int r0 = tid >> 2;
    const char* src = reinterpret_cast<const char*>(ptrs.wq) + (size_t)r0 * 8192 + b * 64 + t * 16;
    const uint32_t dst = ring + 11 * kSlot + r0 * 64 + ((t ^ ((r0 >> 1) & 3)) << 4);
    const uint64_t pol = stream_policy();
#pragma unroll
    for (int i = 0; i < 7; i++)
      asm volatile("cp.async.cg.shared.global.L2::cache_hint.L2::128B [%0], [%1], 16, %2;" ::"r"(dst + i * 4096),
                   "l"(src + (size_t)i * 64 * 8192), "l"(pol)
                   : "memory");
  }
  bar_sync(kBarInit, 288);
  asm volatile("cp.async.mbarrier.arrive.noinc.shared::cta.b64 [%0];" ::"r"(full0) : "memory");

  if (w == 0) {
    float s = 0.f;
#pragma unroll
    for (int i = 0; i < 7; i++) s += lo_f(xw[i]) + hi_f(xw[i]);
#pragma unroll
    for (int o = 16; o; o >>= 1) s += __shfl_xor_sync(0xffffffffu, s, o);
    const float mean = s * (1.f / kD);
    float v = 0.f;
#pragma unroll
    for (int i = 0; i < 7; i++) {
      const float a = lo_f(xw[i]) - mean, c = hi_f(xw[i]) - mean;
      v += a * a + c * c;
    }
#pragma unroll
    for (int o = 16; o; o >>= 1) v += __shfl_xor_sync(0xffffffffu, v, o);
    const float mb = bfr(mean);
    const float rden = rcp_fast(bfr(sqrt_fast(bfr(bfr(v * (1.f / kD)) + 1e-5f))));
#pragma unroll
    for (int i = 0; i < 7; i++) sm.xn[l + 32 * i] = pack2(bfr(lo_f(xw[i]) - mb) * rden, bfr(hi_f(xw[i]) - mb) * rden);
  } else if (w == 1 && l == 0) {
    sm.hs[0][7] = 0.f;
    sm.hs[1][7] = 0.f;
    sm.os[0] = __uint_as_float(1u);
  }
  bar_sync(kBarAttn, 256);
  const uint32_t tag = (epoch + 1) << 2;

  {
    float acc[4] = {0.f, 0.f, 0.f, 0.f};
    const int mt = w & 1, kg = w >> 1;
    mbar_wait(full0);
    const int r0 = 112 * kg + (mi >> 1) * 8 + mr;
    const uint32_t base = ring + 11 * kSlot + r0 * 64 + (((2 * mt + (mi & 1)) ^ ((r0 >> 1) & 3)) << 4);
#pragma unroll
    for (int i = 0; i < 7; i++) {
      uint32_t a[4];
      ldsm4t(a, base + i * 1024);
      mma16816(acc, a, sm.xn[56 * kg + 8 * i + t], sm.xn[56 * kg + 8 * i + 4 + t]);
    }
    if (t == 0) {
      sm.qred[kg][16 * mt + g] = acc[0];
      sm.qred[kg][16 * mt + 8 + g] = acc[2];
    }
    __syncwarp();
    if (l == 0) mbar_arrive(free0 + 8 * 8);
  }
  bar_sync(kBarAttn, 256);
  if (w == 0) {
    const float a = (sm.qred[0][l] + sm.qred[1][l]) + (sm.qred[2][l] + sm.qred[3][l]);
    st_ll1(&g_s.q[h][32 * j + l], __float_as_uint(bfr(a)) | tag);
    bar_arrive(kBarMail, 64);
  }
  mbar_wait(smem_u32(&sm.qready));

  uint32_t bf[16][2];
#pragma unroll
  for (int ks = 0; ks < 16; ks++) {
    bf[ks][0] = sm.qs[(g & 1) * 128 + 8 * ks + t];
    bf[ks][1] = sm.qs[(g & 1) * 128 + 8 * ks + 4 + t];
  }

  {
    float acc[2][4] = {{0.f, 0.f, 0.f, 0.f}, {0.f, 0.f, 0.f, 0.f}};
    mbar_wait(full0 + 8 * (1 + w));
    const uint32_t base = ring + w * kSlot + ((mi & 1) * 8 + mr) * 128;
#pragma unroll
    for (int ks = 0; ks < 16; ks++) {
#pragma unroll
      for (int mt = 0; mt < 2; mt++) {
        uint32_t a[4];
        ldsm4(a, base + (ks >> 2) * 4096 + mt * 2048 + ((((ks & 3) * 2 + (mi >> 1)) ^ mr) << 4));
        mma16816(acc[mt], a, bf[ks][0], bf[ks][1]);
      }
    }
    __syncwarp();
    if (l == 0) mbar_arrive(free0 + 8 * w);
    float m0 = -INFINITY, m1 = -INFINITY;
#pragma unroll
    for (int mt = 0; mt < 2; mt++) {
#pragma unroll
      for (int q = 0; q < 4; q++) acc[mt][q] = bfr(acc[mt][q]) * 0.0625f;
      m0 = fmaxf(m0, fmaxf(acc[mt][0], acc[mt][2]));
      m1 = fmaxf(m1, fmaxf(acc[mt][1], acc[mt][3]));
      if (t == 0) {
        sm.sc[0][32 * w + 16 * mt + g] = acc[mt][0];
        sm.sc[1][32 * w + 16 * mt + g] = acc[mt][1];
        sm.sc[0][32 * w + 16 * mt + 8 + g] = acc[mt][2];
        sm.sc[1][32 * w + 16 * mt + 8 + g] = acc[mt][3];
      }
    }
#pragma unroll
    for (int o = 4; o <= 16; o <<= 1) {
      m0 = fmaxf(m0, __shfl_xor_sync(0xffffffffu, m0, o));
      m1 = fmaxf(m1, __shfl_xor_sync(0xffffffffu, m1, o));
    }
    if (l == 0) {
      sm.wmax[0][w] = m0;
      sm.wmax[1][w] = m1;
    }
  }
  bar_sync(kBarAttn, 256);

  {
    const int hd = tid >> 7;
    const float2 s2 = *reinterpret_cast<const float2*>(&sm.sc[hd][2 * (tid & 127)]);
    const float4 ma = *reinterpret_cast<const float4*>(&sm.wmax[hd][0]);
    const float4 mb = *reinterpret_cast<const float4*>(&sm.wmax[hd][4]);
    const float m = fmaxf(fmaxf(fmaxf(ma.x, ma.y), fmaxf(ma.z, ma.w)), fmaxf(fmaxf(mb.x, mb.y), fmaxf(mb.z, mb.w)));
    const float e0 = __expf(s2.x - m), e1 = __expf(s2.y - m);
    sm.p[hd][tid & 127] = pack2(e0, e1);
    float e = e0 + e1;
#pragma unroll
    for (int o = 16; o; o >>= 1) e += __shfl_xor_sync(0xffffffffu, e, o);
    if (l == 0) {
      sm.wsum[w] = e;
      sm.lmax[hd] = m;
    }
    bar_sync(kBarAttn, 256);
    if (w == 0) {
      const float l0 = (sm.wsum[0] + sm.wsum[1]) + (sm.wsum[2] + sm.wsum[3]);
      const float l1 = (sm.wsum[4] + sm.wsum[5]) + (sm.wsum[6] + sm.wsum[7]);
      st_ll4_if(l == 0, &g_s.st[h][j][0], tagf(sm.lmax[0], tag), tagf(l0, tag), tagf(sm.lmax[1], tag), tagf(l1, tag));
      bar_arrive(kBarMail, 64);
    }
  }
#pragma unroll
  for (int ks = 0; ks < 16; ks++) {
    bf[ks][0] = sm.p[(g >> 1) & 1][8 * ks + t];
    bf[ks][1] = sm.p[(g >> 1) & 1][8 * ks + 4 + t];
  }

  {
    float acc[2][2][4];
#pragma unroll
    for (int q = 0; q < 4; q++) acc[0][0][q] = acc[0][1][q] = acc[1][0][q] = acc[1][1][q] = 0.f;
    const uint32_t off = (w >> 1) * 4096 + ((mi >> 1) * 8 + mr) * 128;
    const int u0 = (w & 1) * 4 + (mi & 1);
    float fac = 0.f;
    uint32_t tag1 = tag | 1;
#pragma unroll
    for (int v = 0; v < 8; v++) {
      uint32_t base = ring + (v < 5 ? 8 + v : v - 5) * kSlot + off;
      uint32_t a0 = base + ((u0 ^ mr) << 4), a1 = base + (((u0 + 2) ^ mr) << 4);
      if (v == 7) {
        mbar_wait(smem_u32(&sm.fready));
        fac = sm.fac[t & 1];
        pin(fac);
        pin(odst);
        pin(tag1);
        pin(a0);
        pin(a1);
      }
      mbar_wait(full0 + 8 * (9 + v));
#pragma unroll
      for (int kk = 0; kk < 2; kk++) {
        uint32_t a[4];
        ldsm4t(a, a0 + kk * 2048);
        mma16816(acc[0][kk], a, bf[2 * v + kk][0], bf[2 * v + kk][1]);
        ldsm4t(a, a1 + kk * 2048);
        mma16816(acc[1][kk], a, bf[2 * v + kk][0], bf[2 * v + kk][1]);
      }
    }
    st_ll4_if(t < 2, odst, tagf((acc[0][0][0] + acc[0][1][0]) * fac, tag1), tagf((acc[0][0][2] + acc[0][1][2]) * fac, tag1),
              tagf((acc[1][0][0] + acc[1][1][0]) * fac, tag1), tagf((acc[1][0][2] + acc[1][1][2]) * fac, tag1));
  }

  if (w == 7) {
    poll_o(1, ((epoch + 1) << 2) | 1);
    return;
  }

  pin(accp);
  {
    float wf[32][2];
    uint32_t osa = smem_u32(&sm.os[0]);
    pin(osa);
    mbar_wait(full0 + 8 * 17);
#pragma unroll
    for (int r = 0; r < 32; r++) {
      const uint32_t v = lds32(ring + 3 * kSlot + r * (kD * 2) + w * 128 + l * 4);
      wf[r][0] = lo_f(v);
      wf[r][1] = hi_f(v);
      pin(wf[r][0]);
      pin(wf[r][1]);
    }
    keep_unpacked(wf, smem_u32(&sm.dummy), epoch);
    float4 o0;
    asm volatile(
        "{\n.reg .pred q;\n.reg .u32 it, f;\n"
        "mov.u32 it, 0;\n"
        "O_AGAIN:\n"
        "ld.volatile.shared.v4.f32 {%0,%1,%2,%3}, [%4];\n"
        "mov.b32 f, %0;\n"
        "and.b32 f, f, 1;\n"
        "setp.eq.u32 q, f, 0;\n"
        "vote.sync.all.pred q, q, 0xffffffff;\n"
        "@q bra O_DONE;\n"
        "add.u32 it, it, 1;\n"
        "setp.lt.u32 q, it, 0x400000;\n"
        "@q bra O_AGAIN;\n"
        "O_DONE:\n}"
        : "=&f"(o0.x), "=&f"(o0.y), "=&f"(o0.z), "=&f"(o0.w)
        : "r"(osa)
        : "memory");
    float a0 = 0.f, a1 = 0.f, c0 = 0.f, c1 = 0.f;
#pragma unroll
    for (int i = 0; i < 8; i++) {
      const float4 o = i ? lds128(osa + 16 * i) : o0;
      a0 = fmaf(o.x, wf[4 * i][0], a0); a1 = fmaf(o.x, wf[4 * i][1], a1);
      c0 = fmaf(o.y, wf[4 * i + 1][0], c0); c1 = fmaf(o.y, wf[4 * i + 1][1], c1);
      a0 = fmaf(o.z, wf[4 * i + 2][0], a0); a1 = fmaf(o.z, wf[4 * i + 2][1], a1);
      c0 = fmaf(o.w, wf[4 * i + 3][0], c0); c1 = fmaf(o.w, wf[4 * i + 3][1], c1);
    }
    red_pair(accp, a0 + c0, a1 + c1);
  }

  if (ffn) {
    float wf[16][2];
    mbar_wait(full0 + 8 * 18);
#pragma unroll
    for (int r = 0; r < 16; r++) {
      const uint32_t v = lds32(ring + 5 * kSlot + r * (kD * 2) + w * 128 + l * 4);
      wf[r][0] = lo_f(v);
      wf[r][1] = hi_f(v);
      pin(wf[r][0]);
      pin(wf[r][1]);
    }
    uint32_t ra = smem_u32(&sm.red[0][0][l]), ha = smem_u32(&sm.hh[w][0]), hs = ha + 4 * (l & 15), nma = smem_u32(&sm.hs[0][0]);
    accp = accf;
    keep_unpacked(wf, smem_u32(&sm.dummy), epoch);
    bar_sync(kBarCs, 448);
    float cs = 0.f;
#pragma unroll
    for (int i = 0; i < 7; i++) cs += __uint_as_float(lds32(ra + 128 * i));
    cs *= -1.f / kD;
    pin(cs); pin(ra); pin(ha); pin(hs); pin(nma); pin(accp);
    sts32_if((__float_as_uint(cs) ^ hs ^ ha ^ (uint32_t)(uintptr_t)accp ^ (uint32_t)((uintptr_t)accp >> 32)) == epoch + 1,
             smem_u32(&sm.dummy), 0.f);
    bar_sync(kBarGu, 480);
    float r[7];
#pragma unroll
    for (int i = 0; i < 7; i++) r[i] = __uint_as_float(lds32(ra + 7 * 128 + 128 * i));
    const float nm = sum4(add4(lds128(nma), lds128(nma + 16)));
    const float gu = bfr(fmaf(nm, cs, ((r[0] + r[1]) + (r[2] + r[3])) + ((r[4] + r[5]) + r[6])));
    sts32(hs, bfr(gu * __shfl_xor_sync(0xffffffffu, gu, 16)));
    __syncwarp();
    float a0 = 0.f, a1 = 0.f, c0 = 0.f, c1 = 0.f;
#pragma unroll
    for (int i = 0; i < 4; i++) {
      const float4 o = lds128(ha + 16 * i);
      a0 = fmaf(o.x, wf[4 * i][0], a0); a1 = fmaf(o.x, wf[4 * i][1], a1);
      c0 = fmaf(o.y, wf[4 * i + 1][0], c0); c1 = fmaf(o.y, wf[4 * i + 1][1], c1);
      a0 = fmaf(o.z, wf[4 * i + 2][0], a0); a1 = fmaf(o.z, wf[4 * i + 2][1], a1);
      c0 = fmaf(o.w, wf[4 * i + 3][0], c0); c1 = fmaf(o.w, wf[4 * i + 3][1], c1);
    }
    a0 += c0;
    a1 += c1;
    float4 old;
    asm volatile("atom.relaxed.gpu.global.v4.f32.add {%0,%1,%2,%3}, [%4], {%5,%6,%7,%8};"
                 : "=f"(old.x), "=f"(old.y), "=f"(old.z), "=f"(old.w)
                 : "l"(accp), "f"(a0), "f"(a1), "f"(1.f), "f"(0.f)
                 : "memory");
    bar_sync(kBarRes, 256);
    float2 hv;
    float r2d;
    asm volatile("ld.volatile.shared.v2.f32 {%0,%1}, [%2];" : "=f"(hv.x), "=f"(hv.y) : "r"(smem_u32(&sm.hv[64 * w + 2 * l])) : "memory");
    asm volatile("ld.volatile.shared.f32 %0, [%1];" : "=f"(r2d) : "r"(smem_u32(&sm.r2d)) : "memory");
    asm volatile("{\n.reg .pred p;\nsetp.eq.f32 p, %2, %3;\n@p st.global.u32 [%0], %1;\n}" ::"l"(ptrs.out + 64 * w + 2 * l),
                 "r"(pack2(hv.x + bfr((old.x + a0) * r2d), hv.y + bfr((old.y + a1) * r2d))), "f"(old.z), "f"((float)(kNFfn - 1))
                 : "memory");
    if (b == 0 && tid == 0) g_s.epoch[0] = epoch >= 2 ? 0 : epoch + 1;
  }
}


constexpr int kCl = 8;
constexpr int kNAtt = 64;
enum { cWq = 0, cTile = 1, cWo = 33, cDn = 35, cGu = 36, cQ = 40, cSt = 41, cFac = 42, cO = 43, cFree = 44, cFreeWq = 76, cNBar = 77 };
constexpr int kClTau = 320;
constexpr int kClT0 = 320;
constexpr int kClEarly = 4;
constexpr int kClWoA = 27;
constexpr int kClWoB = 31;
constexpr int kClGap = 300;
constexpr int kClCap = 13900;
constexpr int kClFfn = 12300;
constexpr int kClFfnGap = 200;

struct ClSmem {
  alignas(16) float sc[2][512];
  alignas(16) uint32_t p[2][256];
  alignas(16) uint32_t qs[256];
  uint32_t xn[224];
  alignas(8) float qred[2][64];
  alignas(16) float wmax[2][8];
  float wsum[8];
  alignas(16) float st[kCl][4];
  alignas(16) float oin[kCl][64];
  float red[2][7][32];
  alignas(16) float hs[2][8];
  alignas(16) float hv[kD];
  float r2d;
  alignas(16) float hh[7][16];
  float lmax[2];
  alignas(16) float dummy[4];
  float fac[2];
  unsigned long long bar[cNBar];
};
constexpr int kClSmemBytes = kNSlot * kSlot + (int)sizeof(ClSmem) + 1024;

__device__ __forceinline__ uint32_t mapa(uint32_t a, int rank) {
  uint32_t r;
  asm("mapa.shared::cluster.u32 %0, %1, %2;" : "=r"(r) : "r"(a), "r"(rank));
  return r;
}
__device__ __forceinline__ void st_async4_if(bool p, uint32_t dst, float a, float b, float c, float d, uint32_t bar) {
  asm volatile(
      "{\n.reg .pred p;\nsetp.ne.u32 p, %6, 0;\n"
      "@p st.async.weak.shared::cluster.mbarrier::complete_tx::bytes.v4.f32 [%0], {%1,%2,%3,%4}, [%5];\n}" ::"r"(dst),
      "f"(a), "f"(b), "f"(c), "f"(d), "r"(bar), "r"((uint32_t)p)
      : "memory");
}
__device__ __forceinline__ void wo_part(uint32_t base, uint32_t bar, uint32_t obar, uint32_t src, uint32_t osa, float* accp,
                                        uint32_t dummy, uint32_t key) {
  float wf[32][2];
  uint32_t dst = osa + 4 * (threadIdx.x & 31);
  pin(src);
  pin(dst);
  pin(osa);
  pin(accp);
  mbar_wait(bar);
#pragma unroll
  for (int r = 0; r < 32; r++) {
    const uint32_t v = lds32(base + ((r >> 2) + 8 * (r & 3)) * (kD * 2));
    wf[r][0] = lo_f(v);
    wf[r][1] = hi_f(v);
    pin(wf[r][0]);
    pin(wf[r][1]);
  }
  keep_unpacked(wf, dummy, key);
  mbar_wait(obar);
  float v[8];
#pragma unroll
  for (int i = 0; i < 8; i++) v[i] = __uint_as_float(lds32(src + 256 * i));
  sts32(dst, bfr(((v[0] + v[1]) + (v[2] + v[3])) + ((v[4] + v[5]) + (v[6] + v[7]))));
  __syncwarp();
  float a0 = 0.f, a1 = 0.f, c0 = 0.f, c1 = 0.f;
#pragma unroll
  for (int i = 0; i < 8; i++) {
    const float4 o = lds128(osa + 16 * i);
    a0 = fmaf(o.x, wf[4 * i][0], a0); a1 = fmaf(o.x, wf[4 * i][1], a1);
    c0 = fmaf(o.y, wf[4 * i + 1][0], c0); c1 = fmaf(o.y, wf[4 * i + 1][1], c1);
    a0 = fmaf(o.z, wf[4 * i + 2][0], a0); a1 = fmaf(o.z, wf[4 * i + 2][1], a1);
    c0 = fmaf(o.w, wf[4 * i + 3][0], c0); c1 = fmaf(o.w, wf[4 * i + 3][1], c1);
  }
  red_pair(accp, a0 + c0, a1 + c1);
}

__global__ void __launch_bounds__(kThreads, 1)
fused_cluster_kernel(const __grid_constant__ Maps maps, const Ptrs ptrs) {
  extern __shared__ uint8_t smem_raw[];
  const uint32_t ring = (smem_u32(smem_raw) + 1023u) & ~1023u;
  ClSmem& sm = *reinterpret_cast<ClSmem*>(smem_raw + (ring - smem_u32(smem_raw)) + kNSlot * kSlot);
  const int tid = threadIdx.x, w = tid >> 5, l = tid & 31;
  const int b = blockIdx.x;
  const int h = b >> 3, rk = b & 7;
  const bool att = b < kNAtt;
  const uint32_t bar0 = smem_u32(&sm.bar[0]);

  if (w == 8) {
    const int row0 = h * kSk + (kSk - kWin) + rk * 32;
    const uint64_t pol = stream_policy();
    if (l == 0) {
      if (att) {
        mbar_init(bar0 + 8 * cTile, 1);
        mbar_init(bar0 + 8 * (cTile + 1), 1);
        asm volatile("fence.proxy.async.shared::cta;" ::: "memory");
        mbar_expect(bar0 + 8 * cTile, kSlot);
        tma3d(ring, &maps.k, 0, row0, 0, bar0 + 8 * cTile, pol);
        mbar_expect(bar0 + 8 * (cTile + 1), kSlot);
        tma3d(ring + kSlot, &maps.k, 0, row0 + 256, 0, bar0 + 8 * (cTile + 1), pol);
      }
      mbar_init(bar0, 256);
#pragma unroll
      for (int i = cTile + 2; i < cNBar; i++) mbar_init(bar0 + 8 * i, i >= cFree + 16 ? 8 : 1);
      mbar_expect(bar0 + 8 * cQ, 1024);
      mbar_expect(bar0 + 8 * cSt, 128);
      mbar_expect(bar0 + 8 * cO, 2048);
      asm volatile("fence.mbarrier_init.release.cluster;" ::: "memory");
      asm volatile("fence.proxy.async.shared::cta;" ::: "memory");
      asm volatile("prefetch.tensormap [%0];" ::"l"(&maps.v) : "memory");
      asm volatile("prefetch.tensormap [%0];" ::"l"(&maps.g) : "memory");
      asm volatile("prefetch.tensormap [%0];" ::"l"(&maps.u) : "memory");
    }
    const uint32_t t0 = __shfl_sync(0xffffffffu, now_ns(), 0) - 100;
    asm volatile("barrier.cluster.arrive.relaxed.aligned;" ::: "memory");
    bar_arrive(kBarInit, kThreads);
    if (l == 0) {
      int spin = 0, due = kClT0 + kClTau;
      if (att) {
#pragma unroll 1
        for (int n = 2; n < 32; n++) {
          due += kClTau;
          const uint32_t bar = bar0 + 8 * (cTile + n);
          while ((int)(now_ns() - t0) < due && !(n >= kClEarly && mbar_test(bar - 8 * kClEarly)) && ++spin < kSpinLimit) {}
          if (n >= 9) mbar_wait1(bar0 + 8 * (n < 13 ? cFreeWq : cFree + n - 13));
          mbar_expect(bar, kSlot);
          tma3d(ring + (n < 13 ? n : n < 26 ? n - 13 : n - 26) * kSlot, n < 16 ? &maps.k : &maps.v, 0, row0 + (n & 15) * 256, 0, bar, pol);
          if (n == kClWoA || n == kClWoB) {
            const int hf = n == kClWoB;
            due += kClTau;
            while ((int)(now_ns() - t0) < due && !mbar_test(bar - 8 * (kClEarly - 1)) && ++spin < kSpinLimit) {}
            mbar_wait1(bar0 + 8 * (cFree + 19 + 2 * hf));
            mbar_wait1(bar0 + 8 * (cFree + 20 + 2 * hf));
            mbar_expect(bar0 + 8 * (cWo + hf), 28672);
            bulk1d(ring + (6 + 2 * hf) * kSlot, ptrs.wo + (size_t)(b * 64 + 32 * hf) * kD, 28672, bar0 + 8 * (cWo + hf), pol);
            due += 3 * kClTau / 4;
          }
        }
        mbar_wait1(bar0 + 8 * (cFree + 23));
        mbar_wait1(bar0 + 8 * (cFree + 24));
        mbar_wait1(bar0 + 8 * (cFree + 25));
      }
      mbar_expect(bar0 + 8 * cDn, 14336);
#pragma unroll
      for (int c = 0; c < 4; c++) mbar_expect(bar0 + 8 * (cGu + c), 7168);
      if (att) {
        mbar_wait1(bar0 + 8 * (cTile + 31));
        due = (int)(now_ns() - t0);
      } else {
        due = kClFfn;
      }
#pragma unroll 1
      for (int c = 0; c < 4; c++) {
        while ((int)(now_ns() - t0) < due && ++spin < kSpinLimit) {}
        due = min(due + (att ? kClGap : kClFfnGap), kClCap);
        tma3d(ring + 10 * kSlot + c * 3584, &maps.g, 16 * b, 0, 4 * c, bar0 + 8 * (cGu + c), pol);
        tma3d(ring + 10 * kSlot + 14336 + c * 3584, &maps.u, 16 * b, 0, 4 * c, bar0 + 8 * (cGu + c), pol);
      }
      while ((int)(now_ns() - t0) < due && ++spin < kSpinLimit) {}
      bulk1d(ring + 12 * kSlot, ptrs.dn + (size_t)b * 16 * kD, 14336, bar0 + 8 * cDn, pol);
    }
    return;
  }
  asm volatile("barrier.cluster.arrive.relaxed.aligned;" ::: "memory");
  uint32_t epoch;
  asm volatile("ld.relaxed.gpu.global.u32 %0, [%1];" : "=r"(epoch) : "l"(&g_s.epoch[0]) : "memory");
  const int g = l >> 2, t = l & 3;
  const int wc = w >= 10 ? w - 10 : w < 7 ? w : 0;
  float* accp = &g_s.hacc[8 * wc + (l >> 2)][4 * (l & 3)];
  float* accf = &g_s.facc[16 * wc + (l >> 1)][4 * (l & 1)];
  const uint32_t dummy = smem_u32(&sm.dummy);

  if (w >= 10) {
    const uint32_t xw = *reinterpret_cast<const uint32_t*>(ptrs.x + 64 * (w - 10) + 2 * l);
    if (b == kNFfn - 1) {
      uint32_t *ah = reinterpret_cast<uint32_t*>(accp), *af = reinterpret_cast<uint32_t*>(accf);
      st_ll4(ah, xw << 16, xw & 0xFFFF0000u, 0, 0);
      st_ll4(af, 0, 0, 0, 0);
      uint32_t tag;
      asm volatile("{\n.reg .pred p, q;\nsetp.ne.u32 p, %1, 0;\nbar.red.or.pred q, %2, 224, p;\nselp.u32 %0, 1, 0, q;\n}"
                   : "=r"(tag)
                   : "r"(ld_poll4(ah).z | ld_poll4(af).z), "n"((int)kBarMail)
                   : "memory");
      tag += (epoch + 1) << 2;
      if (w == 10) st_ll4_if(l < 2, &g_s.ready[4 * l], tag, tag, tag, tag);
    }
    bar_sync(kBarInit, kThreads);
    const int wb = w - 10, rg = (l >> 2) & 3;
    bar_sync(kBarO, 256);
    if (att) {
      wo_part(ring + 8 * kSlot + wb * 128 + l * 4, bar0 + 8 * (cWo + 1), bar0 + 8 * cO, smem_u32(&sm.oin[0][32 + l]),
              smem_u32(&sm.sc[1][32 * wb]), accp, dummy, epoch);
    }
    const uint32_t src = ring + 10 * kSlot + (l >> 4) * 14336 + (4 * wb + rg) * 32 + (l & 3) * 8;
    float wf[16][4];
    float4 cs = make_float4(0.f, 0.f, 0.f, 0.f), hv;
#pragma unroll
    for (int i = 0; i < 16; i++) {
      if ((i & 3) == 0) mbar_wait(bar0 + 8 * (cGu + i / 4));
      if (i == 12) hv = ld_acc(accp);
      uint2 raw;
      asm volatile("ld.shared.v2.u32 {%0,%1}, [%2];" : "=r"(raw.x), "=r"(raw.y) : "r"(src + i * 896) : "memory");
      wf[i][0] = lo_f(raw.x); wf[i][1] = hi_f(raw.x); wf[i][2] = lo_f(raw.y); wf[i][3] = hi_f(raw.y);
      cs.x += wf[i][0]; cs.y += wf[i][1]; cs.z += wf[i][2]; cs.w += wf[i][3];
#pragma unroll
      for (int e = 0; e < 4; e++) pin(wf[i][e]);
      if ((i & 3) == 3 && i < 15) sts32_if(__float_as_uint(sum4(cs)) == epoch + 1, dummy, 0.f);
    }
    uint32_t rdst = smem_u32(&sm.red[0][wb][(l & 16) + 4 * (l & 3) + rg]);
    uint32_t hsa = smem_u32(&sm.hs[0][wb]);
    int sl = 8 * rg;
    pin(rdst);
    pin(accp);
    pin(hsa);
    asm volatile("" : "+r"(sl));
    sts32(rdst, treduce2<8>(cs, l));
    bar_arrive(kBarCs, 448);
    poll_acc(hv, accp, (float)kNCta);
    float4 acc = make_float4(0.f, 0.f, 0.f, 0.f), acc2 = acc;
    float s = (hv.x + hv.w) + hv.y;
#pragma unroll
    for (int i = 0; i < 8; i++) {
      const float f0 = __shfl_sync(0xffffffffu, hv.x, sl + i), f1 = __shfl_sync(0xffffffffu, hv.y, sl + i);
      if (i < 5) s += __shfl_xor_sync(0xffffffffu, s, 1 << i);
      acc.x = fmaf(f0, wf[2 * i][0], acc.x); acc.y = fmaf(f0, wf[2 * i][1], acc.y);
      acc.z = fmaf(f0, wf[2 * i][2], acc.z); acc.w = fmaf(f0, wf[2 * i][3], acc.w);
      acc2.x = fmaf(f1, wf[2 * i + 1][0], acc2.x); acc2.y = fmaf(f1, wf[2 * i + 1][1], acc2.y);
      acc2.z = fmaf(f1, wf[2 * i + 1][2], acc2.z); acc2.w = fmaf(f1, wf[2 * i + 1][3], acc2.w);
    }
    sts32_if(l == 0, hsa, s);
    sts32(rdst + 7 * 128, treduce2<8>(add4(acc, acc2), l));
    bar_arrive(kBarGu, 480);
    {
      uint32_t hd = smem_u32(&sm.hv[64 * wb + 2 * l]);
      asm volatile("st.shared.v2.f32 [%0], {%1,%2};" ::"r"(hd), "f"(hv.x), "f"(hv.y) : "memory");
      asm volatile("ld.volatile.shared.v2.f32 {%0,%1}, [%2];" : "=f"(hv.x), "=f"(hv.y) : "r"(hd) : "memory");
      float q = hv.x * hv.x + hv.y * hv.y;
#pragma unroll
      for (int o = 16; o; o >>= 1) q += __shfl_xor_sync(0xffffffffu, q, o);
      sts32_if(l == 0, hsa + 32, q);
      asm volatile("st.shared.v2.f32 [%0], {%1,%2};" ::"r"(hd), "f"(bfr(lo_f(xw) + bfr(hv.x - lo_f(xw)))),
                   "f"(bfr(hi_f(xw) + bfr(hv.y - hi_f(xw))))
                   : "memory");
      bar_arrive(kBarOwn, 256);
    }
    return;
  }

  if (w == 9) {
    if (l == 0) {
      sm.hs[0][7] = 0.f;
      sm.hs[1][7] = 0.f;
    }
    bar_sync(kBarInit, kThreads);
    {
      const uint32_t tag = (epoch + 1) << 2;
      int it = 0;
      __nanosleep(4000);
#pragma unroll 1
      while (stale4(ld_poll4(&g_s.ready[0]), tag) && ++it < kSpinLimit) __nanosleep(300);
      bar_arrive(kBarO, 256);
    }
    if (att) {
      mbar_wait(bar0 + 8 * cSt);
      const float2 ml = *reinterpret_cast<const float2*>(&sm.st[l & 7][2 * ((l >> 3) & 1)]);
      float M = ml.x;
#pragma unroll
      for (int o = 4; o; o >>= 1) M = fmaxf(M, __shfl_xor_sync(0xffffffffu, M, o));
      const float e = __expf(ml.x - M);
      float L = ml.y * e;
#pragma unroll
      for (int o = 4; o; o >>= 1) L += __shfl_xor_sync(0xffffffffu, L, o);
      if ((l & 7) == rk && l < 16) sm.fac[l >> 3] = __fdividef(e, L);
      __syncwarp();
      if (l == 0) mbar_arrive(bar0 + 8 * cFac);
    }
    bar_sync(kBarGu, 480);
    bar_sync(kBarOwn, 256);
    const float mean = sum4(add4(lds128(smem_u32(&sm.hs[0][0])), lds128(smem_u32(&sm.hs[0][4])))) * (1.f / kD);
    const float q = sum4(add4(lds128(smem_u32(&sm.hs[1][0])), lds128(smem_u32(&sm.hs[1][4]))));
    const float rden = rcp_fast(bfr(sqrt_fast(bfr(bfr(fmaxf(q * (1.f / kD) - mean * mean, 0.f)) + 1e-5f))));
    if (l == 0) sm.r2d = rden * rden;
    bar_arrive(kBarRes, 256);
    return;
  }

  if (att) {
    const int mi = l >> 3, mr = l & 7;
    uint32_t xw[7];
    if (w == 0) {
#pragma unroll
      for (int i = 0; i < 7; i++)
        asm volatile("ld.global.nc.u32 %0, [%1];" : "=r"(xw[i]) : "l"(reinterpret_cast<const uint32_t*>(ptrs.x) + l + 32 * i));
    }
    {
      const int r0 = tid >> 3;
      const char* src = reinterpret_cast<const char*>(ptrs.wq) + (size_t)r0 * 8192 + b * 128 + (tid & 7) * 16;
      const uint32_t dst = ring + 9 * kSlot + r0 * 128 + (((tid ^ r0) & 7) << 4);
      const uint64_t pol = stream_policy();
#pragma unroll
      for (int i = 0; i < 14; i++)
        asm volatile("cp.async.cg.shared.global.L2::cache_hint [%0], [%1], 16, %2;" ::"r"(dst + i * 4096),
                     "l"(src + (size_t)i * 32 * 8192), "l"(pol)
                     : "memory");
    }
    bar_sync(kBarInit, kThreads);
    asm volatile("cp.async.mbarrier.arrive.noinc.shared::cta.b64 [%0];" ::"r"(bar0) : "memory");

    if (w == 0) {
      float s = 0.f;
#pragma unroll
      for (int i = 0; i < 7; i++) s += lo_f(xw[i]) + hi_f(xw[i]);
#pragma unroll
      for (int o = 16; o; o >>= 1) s += __shfl_xor_sync(0xffffffffu, s, o);
      const float mean = s * (1.f / kD);
      float v = 0.f;
#pragma unroll
      for (int i = 0; i < 7; i++) {
        const float a = lo_f(xw[i]) - mean, c = hi_f(xw[i]) - mean;
        v += a * a + c * c;
      }
#pragma unroll
      for (int o = 16; o; o >>= 1) v += __shfl_xor_sync(0xffffffffu, v, o);
      const float mb = bfr(mean);
      const float rden = rcp_fast(bfr(sqrt_fast(bfr(bfr(v * (1.f / kD)) + 1e-5f))));
#pragma unroll
      for (int i = 0; i < 7; i++) sm.xn[l + 32 * i] = pack2(bfr(lo_f(xw[i]) - mb) * rden, bfr(hi_f(xw[i]) - mb) * rden);
      asm volatile("barrier.cluster.wait.acquire.aligned;" ::: "memory");
    }
    bar_sync(kBarAttn, 256);

    {
      float acc[4] = {0.f, 0.f, 0.f, 0.f}, acc2[4] = {0.f, 0.f, 0.f, 0.f};
      const int mt = w & 3, kg = w >> 2;
      mbar_wait(bar0);
      const uint32_t base = ring + 9 * kSlot + (224 * kg + (mi >> 1) * 8 + mr) * 128 + (((2 * mt + (mi & 1)) ^ mr) << 4);
#pragma unroll
      for (int i = 0; i < 14; i++) {
        uint32_t a[4];
        ldsm4t(a, base + i * 2048);
        mma16816((i & 1) ? acc2 : acc, a, sm.xn[112 * kg + 8 * i + t], sm.xn[112 * kg + 8 * i + 4 + t]);
      }
      if (t == 0) {
        sm.qred[kg][16 * mt + g] = acc[0] + acc2[0];
        sm.qred[kg][16 * mt + 8 + g] = acc[2] + acc2[2];
      }
      __syncwarp();
      if (l == 0) mbar_arrive(bar0 + 8 * cFreeWq);
    }
    bar_sync(kBarAttn, 256);
    {
      const float2 a = *reinterpret_cast<const float2*>(&sm.qred[0][2 * l]), c = *reinterpret_cast<const float2*>(&sm.qred[1][2 * l]);
      asm volatile("st.async.weak.shared::cluster.mbarrier::complete_tx::bytes.b32 [%0], %1, [%2];" ::"r"(
                       mapa(smem_u32(&sm.qs[32 * rk + l]), w)),
                   "r"(pack2(a.x + c.x, a.y + c.y)), "r"(mapa(bar0 + 8 * cQ, w))
                   : "memory");
    }
    mbar_wait(bar0 + 8 * cQ);

    {
      uint32_t bf[16][2];
#pragma unroll
      for (int ks = 0; ks < 16; ks++) {
        bf[ks][0] = sm.qs[(g & 1) * 128 + 8 * ks + t];
        bf[ks][1] = sm.qs[(g & 1) * 128 + 8 * ks + 4 + t];
      }
      float m0 = -INFINITY, m1 = -INFINITY;
#pragma unroll 1
      for (int n = w; n < 16; n += 8) {
        float acc[2][4] = {{0.f, 0.f, 0.f, 0.f}, {0.f, 0.f, 0.f, 0.f}};
        mbar_wait(bar0 + 8 * (cTile + n));
        const uint32_t base = ring + (n < 13 ? n : n - 13) * kSlot + ((mi & 1) * 8 + mr) * 128;
#pragma unroll
        for (int ks = 0; ks < 16; ks++) {
#pragma unroll
          for (int mt = 0; mt < 2; mt++) {
            uint32_t a[4];
            ldsm4(a, base + (ks >> 2) * 4096 + mt * 2048 + ((((ks & 3) * 2 + (mi >> 1)) ^ mr) << 4));
            mma16816(acc[mt], a, bf[ks][0], bf[ks][1]);
          }
        }
        __syncwarp();
        if (l == 0) mbar_arrive(bar0 + 8 * (cFree + n));
#pragma unroll
        for (int mt = 0; mt < 2; mt++) {
#pragma unroll
          for (int q = 0; q < 4; q++) acc[mt][q] = bfr(acc[mt][q]) * 0.0625f;
          m0 = fmaxf(m0, fmaxf(acc[mt][0], acc[mt][2]));
          m1 = fmaxf(m1, fmaxf(acc[mt][1], acc[mt][3]));
          if (t == 0) {
            sm.sc[0][32 * n + 16 * mt + g] = acc[mt][0];
            sm.sc[1][32 * n + 16 * mt + g] = acc[mt][1];
            sm.sc[0][32 * n + 16 * mt + 8 + g] = acc[mt][2];
            sm.sc[1][32 * n + 16 * mt + 8 + g] = acc[mt][3];
          }
        }
      }
#pragma unroll
      for (int o = 4; o <= 16; o <<= 1) {
        m0 = fmaxf(m0, __shfl_xor_sync(0xffffffffu, m0, o));
        m1 = fmaxf(m1, __shfl_xor_sync(0xffffffffu, m1, o));
      }
      if (l == 0) {
        sm.wmax[0][w] = m0;
        sm.wmax[1][w] = m1;
      }
    }
    bar_sync(kBarAttn, 256);

    {
      const int hd = tid >> 7;
      const float4 s4 = *reinterpret_cast<const float4*>(&sm.sc[hd][4 * (tid & 127)]);
      const float4 ma = *reinterpret_cast<const float4*>(&sm.wmax[hd][0]);
      const float4 mb = *reinterpret_cast<const float4*>(&sm.wmax[hd][4]);
      const float m = fmaxf(fmaxf(fmaxf(ma.x, ma.y), fmaxf(ma.z, ma.w)), fmaxf(fmaxf(mb.x, mb.y), fmaxf(mb.z, mb.w)));
      const float e0 = __expf(s4.x - m), e1 = __expf(s4.y - m), e2 = __expf(s4.z - m), e3 = __expf(s4.w - m);
      *reinterpret_cast<uint2*>(&sm.p[hd][2 * (tid & 127)]) = make_uint2(pack2(e0, e1), pack2(e2, e3));
      float e = (e0 + e1) + (e2 + e3);
#pragma unroll
      for (int o = 16; o; o >>= 1) e += __shfl_xor_sync(0xffffffffu, e, o);
      if (l == 0) {
        sm.wsum[w] = e;
        sm.lmax[hd] = m;
      }
      bar_sync(kBarAttn, 256);
      if (w == 0) {
        const float l0 = (sm.wsum[0] + sm.wsum[1]) + (sm.wsum[2] + sm.wsum[3]);
        const float l1 = (sm.wsum[4] + sm.wsum[5]) + (sm.wsum[6] + sm.wsum[7]);
        st_async4_if(l < kCl, mapa(smem_u32(&sm.st[rk][0]), l & 7), sm.lmax[0], l0, sm.lmax[1], l1, mapa(bar0 + 8 * cSt, l & 7));
      }
    }

    {
      float acc[2][2][4];
#pragma unroll
      for (int q = 0; q < 4; q++) acc[0][0][q] = acc[0][1][q] = acc[1][0][q] = acc[1][1][q] = 0.f;
      const uint32_t off = ring + (w >> 1) * 4096 + ((mi >> 1) * 8 + mr) * 128;
      const int u0 = (w & 1) * 4 + (mi & 1);
      const uint32_t x0 = (u0 ^ mr) << 4, x1 = ((u0 + 2) ^ mr) << 4;
      const uint32_t pa = smem_u32(&sm.p[(g >> 1) & 1][t]);
      const int dr = 4 * (t & 1) + (w >> 1);
      uint32_t odst = mapa(smem_u32(&sm.oin[rk][32 * (w & 1) + 4 * g]), dr), obar = mapa(bar0 + 8 * cO, dr);
      float fac = 0.f;
      auto tile = [&](int v, uint32_t base, uint32_t b0, uint32_t b1, uint32_t b2, uint32_t b3) {
        mbar_wait(bar0 + 8 * (cTile + 16 + v));
        uint32_t a[4][4];
        ldsm4t(a[0], base + x0);
        ldsm4t(a[1], base + x1);
        ldsm4t(a[2], base + x0 + 2048);
        ldsm4t(a[3], base + x1 + 2048);
        mma16816(acc[0][0], a[0], b0, b1);
        mma16816(acc[1][0], a[1], b0, b1);
        mma16816(acc[0][1], a[2], b2, b3);
        mma16816(acc[1][1], a[3], b2, b3);
      };
#pragma unroll 1
      for (int v = 0; v < 13; v++) {
        tile(v, off + (v < 10 ? v + 3 : v - 10) * kSlot, lds32(pa + 64 * v), lds32(pa + 64 * v + 16), lds32(pa + 64 * v + 32),
             lds32(pa + 64 * v + 48));
        if (v < 10) {
          __syncwarp();
          if (l == 0) mbar_arrive(bar0 + 8 * (cFree + 16 + v));
        }
      }
      uint32_t bl[12];
#pragma unroll
      for (int i = 0; i < 12; i++) bl[i] = lds32(pa + 64 * 13 + 16 * i);
      mbar_wait(bar0 + 8 * cFac);
      fac = sm.fac[t & 1];
      pin(fac);
      pin(odst);
      pin(obar);
#pragma unroll
      for (int v = 13; v < 16; v++) tile(v, off + (v - 10) * kSlot, bl[4 * v - 52], bl[4 * v - 51], bl[4 * v - 50], bl[4 * v - 49]);
      st_async4_if(t < 2, odst, (acc[0][0][0] + acc[0][1][0]) * fac, (acc[0][0][2] + acc[0][1][2]) * fac,
                   (acc[1][0][0] + acc[1][1][0]) * fac, (acc[1][0][2] + acc[1][1][2]) * fac, obar);
    }
    if (w == 7) {
      return;
    }
    wo_part(ring + 6 * kSlot + w * 128 + l * 4, bar0 + 8 * cWo, bar0 + 8 * cO, smem_u32(&sm.oin[0][l]),
            smem_u32(&sm.sc[0][32 * w]), accp, dummy, epoch);
  } else {
    bar_sync(kBarInit, kThreads);
    if (w == 7) {
      return;
    }
  }

  {
    float wf[16][2];
    mbar_wait(bar0 + 8 * cDn);
#pragma unroll
    for (int r = 0; r < 16; r++) {
      const uint32_t v = lds32(ring + 12 * kSlot + r * (kD * 2) + w * 128 + l * 4);
      wf[r][0] = lo_f(v);
      wf[r][1] = hi_f(v);
      pin(wf[r][0]);
      pin(wf[r][1]);
    }
    uint32_t ra = smem_u32(&sm.red[0][0][l]), ha = smem_u32(&sm.hh[w][0]), hs = ha + 4 * (l & 15), nma = smem_u32(&sm.hs[0][0]);
    keep_unpacked(wf, dummy, epoch);
    bar_sync(kBarCs, 448);
    float cs = 0.f;
#pragma unroll
    for (int i = 0; i < 7; i++) cs += __uint_as_float(lds32(ra + 128 * i));
    cs *= -1.f / kD;
    pin(cs); pin(ra); pin(ha); pin(hs); pin(nma); pin(accf);
    sts32_if((__float_as_uint(cs) ^ hs ^ ha ^ (uint32_t)(uintptr_t)accf ^ (uint32_t)((uintptr_t)accf >> 32)) == epoch + 1, dummy, 0.f);
    bar_sync(kBarGu, 480);
    float r[7];
#pragma unroll
    for (int i = 0; i < 7; i++) r[i] = __uint_as_float(lds32(ra + 7 * 128 + 128 * i));
    const float nm = sum4(add4(lds128(nma), lds128(nma + 16)));
    const float gu = bfr(fmaf(nm, cs, ((r[0] + r[1]) + (r[2] + r[3])) + ((r[4] + r[5]) + r[6])));
    sts32(hs, bfr(gu * __shfl_xor_sync(0xffffffffu, gu, 16)));
    __syncwarp();
    float a0 = 0.f, a1 = 0.f, c0 = 0.f, c1 = 0.f;
#pragma unroll
    for (int i = 0; i < 4; i++) {
      const float4 o = lds128(ha + 16 * i);
      a0 = fmaf(o.x, wf[4 * i][0], a0); a1 = fmaf(o.x, wf[4 * i][1], a1);
      c0 = fmaf(o.y, wf[4 * i + 1][0], c0); c1 = fmaf(o.y, wf[4 * i + 1][1], c1);
      a0 = fmaf(o.z, wf[4 * i + 2][0], a0); a1 = fmaf(o.z, wf[4 * i + 2][1], a1);
      c0 = fmaf(o.w, wf[4 * i + 3][0], c0); c1 = fmaf(o.w, wf[4 * i + 3][1], c1);
    }
    a0 += c0;
    a1 += c1;
    float4 old;
    asm volatile("atom.relaxed.gpu.global.v4.f32.add {%0,%1,%2,%3}, [%4], {%5,%6,%7,%8};"
                 : "=f"(old.x), "=f"(old.y), "=f"(old.z), "=f"(old.w)
                 : "l"(accf), "f"(a0), "f"(a1), "f"(1.f), "f"(0.f)
                 : "memory");
    bar_sync(kBarRes, 256);
    float2 hv;
    float r2d;
    asm volatile("ld.volatile.shared.v2.f32 {%0,%1}, [%2];" : "=f"(hv.x), "=f"(hv.y) : "r"(smem_u32(&sm.hv[64 * w + 2 * l])) : "memory");
    asm volatile("ld.volatile.shared.f32 %0, [%1];" : "=f"(r2d) : "r"(smem_u32(&sm.r2d)) : "memory");
    asm volatile("{\n.reg .pred p;\nsetp.eq.f32 p, %2, %3;\n@p st.global.u32 [%0], %1;\n}" ::"l"(ptrs.out + 64 * w + 2 * l),
                 "r"(pack2(hv.x + bfr((old.x + a0) * r2d), hv.y + bfr((old.y + a1) * r2d))), "f"(old.z), "f"((float)(kNFfn - 1))
                 : "memory");
    if (tid == 0 && old.z == (float)(kNFfn - 1)) g_s.epoch[0] = epoch >= 2 ? 0 : epoch + 1;
  }
}

typedef CUresult (*EncodeFn)(CUtensorMap*, CUtensorMapDataType, cuuint32_t, void*, const cuuint64_t*, const cuuint64_t*,
                             const cuuint32_t*, const cuuint32_t*, CUtensorMapInterleave, CUtensorMapSwizzle,
                             CUtensorMapL2promotion, CUtensorMapFloatOOBfill);

void make_map(EncodeFn enc, CUtensorMap* m, const void* base) {
  cuuint64_t dims[3] = {64, 8ull * kSk, 4};
  cuuint64_t str[2] = {kDh * 2, 128};
  cuuint32_t box[3] = {64, 32, 4};
  cuuint32_t es[3] = {1, 1, 1};
  enc(m, CU_TENSOR_MAP_DATA_TYPE_BFLOAT16, 3, const_cast<void*>(base), dims, str, box, es, CU_TENSOR_MAP_INTERLEAVE_NONE,
      CU_TENSOR_MAP_SWIZZLE_128B, CU_TENSOR_MAP_L2_PROMOTION_L2_256B, CU_TENSOR_MAP_FLOAT_OOB_FILL_NONE);
}

void make_map_ffn(EncodeFn enc, CUtensorMap* m, const void* base) {
  cuuint64_t dims[3] = {kFF, kD / 16, 16};
  cuuint64_t str[2] = {16 * kFF * 2, kFF * 2};
  cuuint32_t box[3] = {16, kD / 16, 4};
  cuuint32_t es[3] = {1, 1, 1};
  enc(m, CU_TENSOR_MAP_DATA_TYPE_BFLOAT16, 3, const_cast<void*>(base), dims, str, box, es, CU_TENSOR_MAP_INTERLEAVE_NONE,
      CU_TENSOR_MAP_SWIZZLE_NONE, CU_TENSOR_MAP_L2_PROMOTION_L2_128B, CU_TENSOR_MAP_FLOAT_OOB_FILL_NONE);
}

}

extern "C" void kernel_launch(void* const* d_in, const int* in_sizes, int n_in, void* d_out, int out_size) {
  (void)in_sizes; (void)n_in; (void)out_size;
  static Maps maps;
  static const void* keys[4];
  static EncodeFn enc = nullptr;
  static int nclusters = 0;
  cudaLaunchAttribute attr;
  attr.id = cudaLaunchAttributeClusterDimension;
  attr.val.clusterDim.x = kCl;
  attr.val.clusterDim.y = attr.val.clusterDim.z = 1;
  cudaLaunchConfig_t cfg = {};
  cfg.gridDim = dim3(kNFfn);
  cfg.blockDim = dim3(kThreads);
  cfg.dynamicSmemBytes = kClSmemBytes;
  cfg.stream = cudaStreamPerThread;
  cfg.attrs = &attr;
  cfg.numAttrs = 1;
  if (!enc) {
    void* fn = nullptr;
    cudaDriverEntryPointQueryResult qr;
    cudaGetDriverEntryPoint("cuTensorMapEncodeTiled", &fn, cudaEnableDefault, &qr);
    enc = (EncodeFn)fn;
    cudaFuncSetAttribute(fused_decode_kernel, cudaFuncAttributeMaxDynamicSharedMemorySize, kSmemBytes);
    cudaFuncSetAttribute(fused_cluster_kernel, cudaFuncAttributeMaxDynamicSharedMemorySize, kClSmemBytes);
    cudaOccupancyMaxActiveClusters(&nclusters, fused_cluster_kernel, &cfg);
    (void)cudaGetLastError();
  }
  if (keys[0] != d_in[1] || keys[1] != d_in[2] || keys[2] != d_in[6] || keys[3] != d_in[7]) {
    make_map(enc, &maps.k, d_in[1]);
    make_map(enc, &maps.v, d_in[2]);
    make_map_ffn(enc, &maps.g, d_in[6]);
    make_map_ffn(enc, &maps.u, d_in[7]);
    keys[0] = d_in[1];
    keys[1] = d_in[2];
    keys[2] = d_in[6];
    keys[3] = d_in[7];
  }
  typedef const __nv_bfloat16* P;
  Ptrs ptrs{(P)d_in[0], (P)d_in[3], (P)d_in[4], (P)d_in[8], (__nv_bfloat16*)d_out};
  if (nclusters >= kNFfn / kCl)
    cudaLaunchKernelEx(&cfg, fused_cluster_kernel, maps, ptrs);
  else
    fused_decode_kernel<<<kNCta, kThreads, kSmemBytes, cudaStreamPerThread>>>(maps, ptrs);
}
```
